```python
import torch

def _softmax(x, axis=-1):
    return torch.softmax(x, dim=axis)
def _gelu(x):
    return torch.nn.functional.gelu(x, approximate="tanh")
def _silu(x):
    return torch.nn.functional.silu(x)
def _sigmoid(x):
    return torch.sigmoid(x)
def _layernorm(x, axis=-1, eps=1e-5):
    m = x.mean(dim=axis, keepdim=True)
    v = x.var(dim=axis, keepdim=True, unbiased=False)
    return (x - m) / torch.sqrt(v + eps)
def _scatter_add(tgt, idx, src, axis=0):
    return tgt.clone().index_add_(axis, idx, src)
def _segment_sum(src, seg, n):
    out = torch.zeros((n,) + src.shape[1:], dtype=src.dtype)
    return out.index_add_(0, seg, src)
def _pad(x, pw):
    flat = tuple(v for pair in reversed(pw) for v in pair)
    return torch.nn.functional.pad(x, flat)

kernel_name = 'sequential_preLN__ssm_conv_h3__moe_arch_mod__prompt'

def setup_inputs():

    _w = (lambda a: (lambda t: t.to(torch.bfloat16) if t.is_floating_point() else t)(torch.as_tensor(a)))
    def _A_setup():
        B, S, D = 1, 2048, 640
        ks = 4
        return {
            "q": _w((lambda *s: torch.randn(*s, dtype=torch.bfloat16) * 0.05)(B, S, D)),
            "k": _w((lambda *s: torch.randn(*s, dtype=torch.bfloat16) * 0.2)(B, S, D)),
            "v": _w((lambda *s: torch.randn(*s, dtype=torch.bfloat16) * 0.2)(B, S, D)),
            "shift_k": _w((lambda *s: torch.randn(*s, dtype=torch.bfloat16) * 0.2)(D, ks) * 0.5),
            "ssm_k": _w((lambda *s: torch.randn(*s, dtype=torch.bfloat16) * 0.8)(D, S) * (1.0 / S ** 0.5)),
            "ssm_D": _w((lambda *s: torch.randn(*s, dtype=torch.bfloat16) * 0.2)(D)),
        }
    _A_in = _A_setup()

    def _B_setup():
        B, S, D, F, C = 1, 2048, 640, 1536, 1
        return {
            "x": _w((lambda *s: torch.randn(*s, dtype=torch.bfloat16) * 0.05)(B, S, D)),
            "w_r": _w((lambda *s: torch.randn(*s, dtype=torch.bfloat16) * 0.05)(D)),
            "w_gate": _w((lambda *s: torch.randn(*s, dtype=torch.bfloat16) * 0.05)(D, F)),
            "w_up": _w((lambda *s: torch.randn(*s, dtype=torch.bfloat16) * 0.05)(D, F)),
            "w_down": _w((lambda *s: torch.randn(*s, dtype=torch.bfloat16) * 0.05)(F, D)),
        }
    _B_in = _B_setup()

    return {
        "A_q": _A_in["q"],
        "A_k": _A_in["k"],
        "A_v": _A_in["v"],
        "A_shift_k": _A_in["shift_k"],
        "A_ssm_k": _A_in["ssm_k"],
        "A_ssm_D": _A_in["ssm_D"],
        "B_x": _B_in["x"],
        "B_w_r": _B_in["w_r"],
        "B_w_gate": _B_in["w_gate"],
        "B_w_up": _B_in["w_up"],
        "B_w_down": _B_in["w_down"],
    }

def reference(A_q, A_k, A_v, A_shift_k, A_ssm_k, A_ssm_D, B_x, B_w_r, B_w_gate, B_w_up, B_w_down):
    def _A_ref(q, k, v, shift_k, ssm_k, ssm_D):
        B, S, D = q.shape
        ks = shift_k.shape[-1]
        k_pad = _pad(k, ((0, 0), (ks - 1, 0), (0, 0)))
        k_shift = torch.zeros_like(k)
        for t in range(ks):
            k_shift = k_shift + k_pad[:, t:t + S, :] * shift_k[:, ks - 1 - t][None, None, :]
        kv = k_shift * v
        L = 2 * S
        kv_pad = _pad(kv, ((0, 0), (0, S), (0, 0)))
        kf_pad = _pad(ssm_k, ((0, 0), (0, S)))
        kv_f = (lambda x, axes=(-2,-1): torch.fft.rfft2(x.float(), dim=axes))(kv_pad[:, None, :, :], axes=(1, 2))
        kf_f = (lambda x, axes=(-2,-1): torch.fft.rfft2(x.float(), dim=axes))(kf_pad[:, None, :], axes=(1, 2))
        kf_f = (lambda x, *d: x.permute(*d))(kf_f, 1, 2, 0)
        y_f = kv_f * kf_f[None, :, :, :]
        y = (lambda x, s, axes=(-2,-1): torch.fft.irfft2(x, s=s, dim=axes).to(torch.bfloat16))(y_f, (1, L), axes=(1, 2))[:, 0, :S, :]
        y = y + kv * ssm_D[None, None, :]
        return q * y

    def _B_ref(x, w_r, w_gate, w_up, w_down):
        B, S, D = x.shape
        C = 1
        r = x @ w_r
        idx = torch.argsort(-r, axis=-1)[:, :C]
        idx_e = (lambda x, n, axis: torch.repeat_interleave(x, n, dim=axis))(idx.reshape(B, C, 1), D, axis=2)
        x_sel = (lambda x, i, axis: torch.take_along_dim(x, i, dim=axis))(x, idx_e, axis=1)
        g = _silu(x_sel @ w_gate)
        u = x_sel @ w_up
        y = (g * u) @ w_down
        r_sel = _sigmoid((lambda x, i, axis: torch.take_along_dim(x, i, dim=axis))(r, idx, axis=1))
        y = y * r_sel.reshape(B, C, 1)
        b_off = (torch.arange(B) * S).reshape(B, 1)
        flat_idx = (idx + b_off).reshape(B * C)
        zero = (x * 0.0).reshape(B * S, D)
        upd = _scatter_add(zero, flat_idx, y.reshape(B * C, D), axis=0)
        return x + upd.reshape(B, S, D)

    x = A_q
    h = x + _A_ref(_layernorm(x, axis=-1), A_k, A_v, A_shift_k, A_ssm_k, A_ssm_D)
    h2 = h + _B_ref(_layernorm(h, axis=-1), B_w_r, B_w_gate, B_w_up, B_w_down)
    return h2
```

```cpp
#include <cuda_runtime.h>
#include <cuda.h>
#include <cuda_bf16.h>
#include <stdint.h>

typedef __nv_bfloat16 bf16;
constexpr int S_  = 2048;
constexpr int D_  = 640;
constexpr int F_  = 1536;
constexpr int NCTA = 128;
constexpr int CH  = 5;
constexpr int RPB = 16;
constexpr int NT  = 512;
constexpr int SPIN_MAX = 1 << 20;
constexpr int MB_SPIN_MAX = 1 << 18;

template<int N> struct WG;
template<> struct WG<8> { static __device__ __forceinline__ void rs(float* d, uint32_t a0, uint32_t a1, uint32_t a2, uint32_t a3, uint64_t b, int sc) {
  asm volatile("{\n.reg .pred p;\nsetp.ne.b32 p, %9, 0;\nwgmma.mma_async.sync.aligned.m64n8k16.f32.bf16.bf16 {%0, %1, %2, %3}, {%4, %5, %6, %7}, %8, p, 1, 1, 0;\n}\n"
    : "+f"(d[0]), "+f"(d[1]), "+f"(d[2]), "+f"(d[3])
    : "r"(a0), "r"(a1), "r"(a2), "r"(a3), "l"(b), "r"(sc)); } };
template<> struct WG<16> { static __device__ __forceinline__ void rs(float* d, uint32_t a0, uint32_t a1, uint32_t a2, uint32_t a3, uint64_t b, int sc) {
  asm volatile("{\n.reg .pred p;\nsetp.ne.b32 p, %13, 0;\nwgmma.mma_async.sync.aligned.m64n16k16.f32.bf16.bf16 {%0, %1, %2, %3, %4, %5, %6, %7}, {%8, %9, %10, %11}, %12, p, 1, 1, 0;\n}\n"
    : "+f"(d[0]), "+f"(d[1]), "+f"(d[2]), "+f"(d[3]), "+f"(d[4]), "+f"(d[5]), "+f"(d[6]), "+f"(d[7])
    : "r"(a0), "r"(a1), "r"(a2), "r"(a3), "l"(b), "r"(sc)); } };
template<> struct WG<24> { static __device__ __forceinline__ void rs(float* d, uint32_t a0, uint32_t a1, uint32_t a2, uint32_t a3, uint64_t b, int sc) {
  asm volatile("{\n.reg .pred p;\nsetp.ne.b32 p, %17, 0;\nwgmma.mma_async.sync.aligned.m64n24k16.f32.bf16.bf16 {%0, %1, %2, %3, %4, %5, %6, %7, %8, %9, %10, %11}, {%12, %13, %14, %15}, %16, p, 1, 1, 0;\n}\n"
    : "+f"(d[0]), "+f"(d[1]), "+f"(d[2]), "+f"(d[3]), "+f"(d[4]), "+f"(d[5]), "+f"(d[6]), "+f"(d[7]), "+f"(d[8]), "+f"(d[9]), "+f"(d[10]), "+f"(d[11])
    : "r"(a0), "r"(a1), "r"(a2), "r"(a3), "l"(b), "r"(sc)); } };
template<> struct WG<32> { static __device__ __forceinline__ void rs(float* d, uint32_t a0, uint32_t a1, uint32_t a2, uint32_t a3, uint64_t b, int sc) {
  asm volatile("{\n.reg .pred p;\nsetp.ne.b32 p, %21, 0;\nwgmma.mma_async.sync.aligned.m64n32k16.f32.bf16.bf16 {%0, %1, %2, %3, %4, %5, %6, %7, %8, %9, %10, %11, %12, %13, %14, %15}, {%16, %17, %18, %19}, %20, p, 1, 1, 0;\n}\n"
    : "+f"(d[0]), "+f"(d[1]), "+f"(d[2]), "+f"(d[3]), "+f"(d[4]), "+f"(d[5]), "+f"(d[6]), "+f"(d[7]), "+f"(d[8]), "+f"(d[9]), "+f"(d[10]), "+f"(d[11]), "+f"(d[12]), "+f"(d[13]), "+f"(d[14]), "+f"(d[15])
    : "r"(a0), "r"(a1), "r"(a2), "r"(a3), "l"(b), "r"(sc)); } };
template<> struct WG<40> { static __device__ __forceinline__ void rs(float* d, uint32_t a0, uint32_t a1, uint32_t a2, uint32_t a3, uint64_t b, int sc) {
  asm volatile("{\n.reg .pred p;\nsetp.ne.b32 p, %25, 0;\nwgmma.mma_async.sync.aligned.m64n40k16.f32.bf16.bf16 {%0, %1, %2, %3, %4, %5, %6, %7, %8, %9, %10, %11, %12, %13, %14, %15, %16, %17, %18, %19}, {%20, %21, %22, %23}, %24, p, 1, 1, 0;\n}\n"
    : "+f"(d[0]), "+f"(d[1]), "+f"(d[2]), "+f"(d[3]), "+f"(d[4]), "+f"(d[5]), "+f"(d[6]), "+f"(d[7]), "+f"(d[8]), "+f"(d[9]), "+f"(d[10]), "+f"(d[11]), "+f"(d[12]), "+f"(d[13]), "+f"(d[14]), "+f"(d[15]), "+f"(d[16]), "+f"(d[17]), "+f"(d[18]), "+f"(d[19])
    : "r"(a0), "r"(a1), "r"(a2), "r"(a3), "l"(b), "r"(sc)); } };
template<> struct WG<48> { static __device__ __forceinline__ void rs(float* d, uint32_t a0, uint32_t a1, uint32_t a2, uint32_t a3, uint64_t b, int sc) {
  asm volatile("{\n.reg .pred p;\nsetp.ne.b32 p, %29, 0;\nwgmma.mma_async.sync.aligned.m64n48k16.f32.bf16.bf16 {%0, %1, %2, %3, %4, %5, %6, %7, %8, %9, %10, %11, %12, %13, %14, %15, %16, %17, %18, %19, %20, %21, %22, %23}, {%24, %25, %26, %27}, %28, p, 1, 1, 0;\n}\n"
    : "+f"(d[0]), "+f"(d[1]), "+f"(d[2]), "+f"(d[3]), "+f"(d[4]), "+f"(d[5]), "+f"(d[6]), "+f"(d[7]), "+f"(d[8]), "+f"(d[9]), "+f"(d[10]), "+f"(d[11]), "+f"(d[12]), "+f"(d[13]), "+f"(d[14]), "+f"(d[15]), "+f"(d[16]), "+f"(d[17]), "+f"(d[18]), "+f"(d[19]), "+f"(d[20]), "+f"(d[21]), "+f"(d[22]), "+f"(d[23])
    : "r"(a0), "r"(a1), "r"(a2), "r"(a3), "l"(b), "r"(sc)); } };
template<> struct WG<56> { static __device__ __forceinline__ void rs(float* d, uint32_t a0, uint32_t a1, uint32_t a2, uint32_t a3, uint64_t b, int sc) {
  asm volatile("{\n.reg .pred p;\nsetp.ne.b32 p, %33, 0;\nwgmma.mma_async.sync.aligned.m64n56k16.f32.bf16.bf16 {%0, %1, %2, %3, %4, %5, %6, %7, %8, %9, %10, %11, %12, %13, %14, %15, %16, %17, %18, %19, %20, %21, %22, %23, %24, %25, %26, %27}, {%28, %29, %30, %31}, %32, p, 1, 1, 0;\n}\n"
    : "+f"(d[0]), "+f"(d[1]), "+f"(d[2]), "+f"(d[3]), "+f"(d[4]), "+f"(d[5]), "+f"(d[6]), "+f"(d[7]), "+f"(d[8]), "+f"(d[9]), "+f"(d[10]), "+f"(d[11]), "+f"(d[12]), "+f"(d[13]), "+f"(d[14]), "+f"(d[15]), "+f"(d[16]), "+f"(d[17]), "+f"(d[18]), "+f"(d[19]), "+f"(d[20]), "+f"(d[21]), "+f"(d[22]), "+f"(d[23]), "+f"(d[24]), "+f"(d[25]), "+f"(d[26]), "+f"(d[27])
    : "r"(a0), "r"(a1), "r"(a2), "r"(a3), "l"(b), "r"(sc)); } };
template<> struct WG<64> { static __device__ __forceinline__ void rs(float* d, uint32_t a0, uint32_t a1, uint32_t a2, uint32_t a3, uint64_t b, int sc) {
  asm volatile("{\n.reg .pred p;\nsetp.ne.b32 p, %37, 0;\nwgmma.mma_async.sync.aligned.m64n64k16.f32.bf16.bf16 {%0, %1, %2, %3, %4, %5, %6, %7, %8, %9, %10, %11, %12, %13, %14, %15, %16, %17, %18, %19, %20, %21, %22, %23, %24, %25, %26, %27, %28, %29, %30, %31}, {%32, %33, %34, %35}, %36, p, 1, 1, 0;\n}\n"
    : "+f"(d[0]), "+f"(d[1]), "+f"(d[2]), "+f"(d[3]), "+f"(d[4]), "+f"(d[5]), "+f"(d[6]), "+f"(d[7]), "+f"(d[8]), "+f"(d[9]), "+f"(d[10]), "+f"(d[11]), "+f"(d[12]), "+f"(d[13]), "+f"(d[14]), "+f"(d[15]), "+f"(d[16]), "+f"(d[17]), "+f"(d[18]), "+f"(d[19]), "+f"(d[20]), "+f"(d[21]), "+f"(d[22]), "+f"(d[23]), "+f"(d[24]), "+f"(d[25]), "+f"(d[26]), "+f"(d[27]), "+f"(d[28]), "+f"(d[29]), "+f"(d[30]), "+f"(d[31])
    : "r"(a0), "r"(a1), "r"(a2), "r"(a3), "l"(b), "r"(sc)); } };
template<> struct WG<72> { static __device__ __forceinline__ void rs(float* d, uint32_t a0, uint32_t a1, uint32_t a2, uint32_t a3, uint64_t b, int sc) {
  asm volatile("{\n.reg .pred p;\nsetp.ne.b32 p, %41, 0;\nwgmma.mma_async.sync.aligned.m64n72k16.f32.bf16.bf16 {%0, %1, %2, %3, %4, %5, %6, %7, %8, %9, %10, %11, %12, %13, %14, %15, %16, %17, %18, %19, %20, %21, %22, %23, %24, %25, %26, %27, %28, %29, %30, %31, %32, %33, %34, %35}, {%36, %37, %38, %39}, %40, p, 1, 1, 0;\n}\n"
    : "+f"(d[0]), "+f"(d[1]), "+f"(d[2]), "+f"(d[3]), "+f"(d[4]), "+f"(d[5]), "+f"(d[6]), "+f"(d[7]), "+f"(d[8]), "+f"(d[9]), "+f"(d[10]), "+f"(d[11]), "+f"(d[12]), "+f"(d[13]), "+f"(d[14]), "+f"(d[15]), "+f"(d[16]), "+f"(d[17]), "+f"(d[18]), "+f"(d[19]), "+f"(d[20]), "+f"(d[21]), "+f"(d[22]), "+f"(d[23]), "+f"(d[24]), "+f"(d[25]), "+f"(d[26]), "+f"(d[27]), "+f"(d[28]), "+f"(d[29]), "+f"(d[30]), "+f"(d[31]), "+f"(d[32]), "+f"(d[33]), "+f"(d[34]), "+f"(d[35])
    : "r"(a0), "r"(a1), "r"(a2), "r"(a3), "l"(b), "r"(sc)); } };
template<> struct WG<80> { static __device__ __forceinline__ void rs(float* d, uint32_t a0, uint32_t a1, uint32_t a2, uint32_t a3, uint64_t b, int sc) {
  asm volatile("{\n.reg .pred p;\nsetp.ne.b32 p, %45, 0;\nwgmma.mma_async.sync.aligned.m64n80k16.f32.bf16.bf16 {%0, %1, %2, %3, %4, %5, %6, %7, %8, %9, %10, %11, %12, %13, %14, %15, %16, %17, %18, %19, %20, %21, %22, %23, %24, %25, %26, %27, %28, %29, %30, %31, %32, %33, %34, %35, %36, %37, %38, %39}, {%40, %41, %42, %43}, %44, p, 1, 1, 0;\n}\n"
    : "+f"(d[0]), "+f"(d[1]), "+f"(d[2]), "+f"(d[3]), "+f"(d[4]), "+f"(d[5]), "+f"(d[6]), "+f"(d[7]), "+f"(d[8]), "+f"(d[9]), "+f"(d[10]), "+f"(d[11]), "+f"(d[12]), "+f"(d[13]), "+f"(d[14]), "+f"(d[15]), "+f"(d[16]), "+f"(d[17]), "+f"(d[18]), "+f"(d[19]), "+f"(d[20]), "+f"(d[21]), "+f"(d[22]), "+f"(d[23]), "+f"(d[24]), "+f"(d[25]), "+f"(d[26]), "+f"(d[27]), "+f"(d[28]), "+f"(d[29]), "+f"(d[30]), "+f"(d[31]), "+f"(d[32]), "+f"(d[33]), "+f"(d[34]), "+f"(d[35]), "+f"(d[36]), "+f"(d[37]), "+f"(d[38]), "+f"(d[39])
    : "r"(a0), "r"(a1), "r"(a2), "r"(a3), "l"(b), "r"(sc)); } };
template<> struct WG<88> { static __device__ __forceinline__ void rs(float* d, uint32_t a0, uint32_t a1, uint32_t a2, uint32_t a3, uint64_t b, int sc) {
  asm volatile("{\n.reg .pred p;\nsetp.ne.b32 p, %49, 0;\nwgmma.mma_async.sync.aligned.m64n88k16.f32.bf16.bf16 {%0, %1, %2, %3, %4, %5, %6, %7, %8, %9, %10, %11, %12, %13, %14, %15, %16, %17, %18, %19, %20, %21, %22, %23, %24, %25, %26, %27, %28, %29, %30, %31, %32, %33, %34, %35, %36, %37, %38, %39, %40, %41, %42, %43}, {%44, %45, %46, %47}, %48, p, 1, 1, 0;\n}\n"
    : "+f"(d[0]), "+f"(d[1]), "+f"(d[2]), "+f"(d[3]), "+f"(d[4]), "+f"(d[5]), "+f"(d[6]), "+f"(d[7]), "+f"(d[8]), "+f"(d[9]), "+f"(d[10]), "+f"(d[11]), "+f"(d[12]), "+f"(d[13]), "+f"(d[14]), "+f"(d[15]), "+f"(d[16]), "+f"(d[17]), "+f"(d[18]), "+f"(d[19]), "+f"(d[20]), "+f"(d[21]), "+f"(d[22]), "+f"(d[23]), "+f"(d[24]), "+f"(d[25]), "+f"(d[26]), "+f"(d[27]), "+f"(d[28]), "+f"(d[29]), "+f"(d[30]), "+f"(d[31]), "+f"(d[32]), "+f"(d[33]), "+f"(d[34]), "+f"(d[35]), "+f"(d[36]), "+f"(d[37]), "+f"(d[38]), "+f"(d[39]), "+f"(d[40]), "+f"(d[41]), "+f"(d[42]), "+f"(d[43])
    : "r"(a0), "r"(a1), "r"(a2), "r"(a3), "l"(b), "r"(sc)); } };
template<> struct WG<96> { static __device__ __forceinline__ void rs(float* d, uint32_t a0, uint32_t a1, uint32_t a2, uint32_t a3, uint64_t b, int sc) {
  asm volatile("{\n.reg .pred p;\nsetp.ne.b32 p, %53, 0;\nwgmma.mma_async.sync.aligned.m64n96k16.f32.bf16.bf16 {%0, %1, %2, %3, %4, %5, %6, %7, %8, %9, %10, %11, %12, %13, %14, %15, %16, %17, %18, %19, %20, %21, %22, %23, %24, %25, %26, %27, %28, %29, %30, %31, %32, %33, %34, %35, %36, %37, %38, %39, %40, %41, %42, %43, %44, %45, %46, %47}, {%48, %49, %50, %51}, %52, p, 1, 1, 0;\n}\n"
    : "+f"(d[0]), "+f"(d[1]), "+f"(d[2]), "+f"(d[3]), "+f"(d[4]), "+f"(d[5]), "+f"(d[6]), "+f"(d[7]), "+f"(d[8]), "+f"(d[9]), "+f"(d[10]), "+f"(d[11]), "+f"(d[12]), "+f"(d[13]), "+f"(d[14]), "+f"(d[15]), "+f"(d[16]), "+f"(d[17]), "+f"(d[18]), "+f"(d[19]), "+f"(d[20]), "+f"(d[21]), "+f"(d[22]), "+f"(d[23]), "+f"(d[24]), "+f"(d[25]), "+f"(d[26]), "+f"(d[27]), "+f"(d[28]), "+f"(d[29]), "+f"(d[30]), "+f"(d[31]), "+f"(d[32]), "+f"(d[33]), "+f"(d[34]), "+f"(d[35]), "+f"(d[36]), "+f"(d[37]), "+f"(d[38]), "+f"(d[39]), "+f"(d[40]), "+f"(d[41]), "+f"(d[42]), "+f"(d[43]), "+f"(d[44]), "+f"(d[45]), "+f"(d[46]), "+f"(d[47])
    : "r"(a0), "r"(a1), "r"(a2), "r"(a3), "l"(b), "r"(sc)); } };
template<> struct WG<104> { static __device__ __forceinline__ void rs(float* d, uint32_t a0, uint32_t a1, uint32_t a2, uint32_t a3, uint64_t b, int sc) {
  asm volatile("{\n.reg .pred p;\nsetp.ne.b32 p, %57, 0;\nwgmma.mma_async.sync.aligned.m64n104k16.f32.bf16.bf16 {%0, %1, %2, %3, %4, %5, %6, %7, %8, %9, %10, %11, %12, %13, %14, %15, %16, %17, %18, %19, %20, %21, %22, %23, %24, %25, %26, %27, %28, %29, %30, %31, %32, %33, %34, %35, %36, %37, %38, %39, %40, %41, %42, %43, %44, %45, %46, %47, %48, %49, %50, %51}, {%52, %53, %54, %55}, %56, p, 1, 1, 0;\n}\n"
    : "+f"(d[0]), "+f"(d[1]), "+f"(d[2]), "+f"(d[3]), "+f"(d[4]), "+f"(d[5]), "+f"(d[6]), "+f"(d[7]), "+f"(d[8]), "+f"(d[9]), "+f"(d[10]), "+f"(d[11]), "+f"(d[12]), "+f"(d[13]), "+f"(d[14]), "+f"(d[15]), "+f"(d[16]), "+f"(d[17]), "+f"(d[18]), "+f"(d[19]), "+f"(d[20]), "+f"(d[21]), "+f"(d[22]), "+f"(d[23]), "+f"(d[24]), "+f"(d[25]), "+f"(d[26]), "+f"(d[27]), "+f"(d[28]), "+f"(d[29]), "+f"(d[30]), "+f"(d[31]), "+f"(d[32]), "+f"(d[33]), "+f"(d[34]), "+f"(d[35]), "+f"(d[36]), "+f"(d[37]), "+f"(d[38]), "+f"(d[39]), "+f"(d[40]), "+f"(d[41]), "+f"(d[42]), "+f"(d[43]), "+f"(d[44]), "+f"(d[45]), "+f"(d[46]), "+f"(d[47]), "+f"(d[48]), "+f"(d[49]), "+f"(d[50]), "+f"(d[51])
    : "r"(a0), "r"(a1), "r"(a2), "r"(a3), "l"(b), "r"(sc)); } };
template<> struct WG<112> { static __device__ __forceinline__ void rs(float* d, uint32_t a0, uint32_t a1, uint32_t a2, uint32_t a3, uint64_t b, int sc) {
  asm volatile("{\n.reg .pred p;\nsetp.ne.b32 p, %61, 0;\nwgmma.mma_async.sync.aligned.m64n112k16.f32.bf16.bf16 {%0, %1, %2, %3, %4, %5, %6, %7, %8, %9, %10, %11, %12, %13, %14, %15, %16, %17, %18, %19, %20, %21, %22, %23, %24, %25, %26, %27, %28, %29, %30, %31, %32, %33, %34, %35, %36, %37, %38, %39, %40, %41, %42, %43, %44, %45, %46, %47, %48, %49, %50, %51, %52, %53, %54, %55}, {%56, %57, %58, %59}, %60, p, 1, 1, 0;\n}\n"
    : "+f"(d[0]), "+f"(d[1]), "+f"(d[2]), "+f"(d[3]), "+f"(d[4]), "+f"(d[5]), "+f"(d[6]), "+f"(d[7]), "+f"(d[8]), "+f"(d[9]), "+f"(d[10]), "+f"(d[11]), "+f"(d[12]), "+f"(d[13]), "+f"(d[14]), "+f"(d[15]), "+f"(d[16]), "+f"(d[17]), "+f"(d[18]), "+f"(d[19]), "+f"(d[20]), "+f"(d[21]), "+f"(d[22]), "+f"(d[23]), "+f"(d[24]), "+f"(d[25]), "+f"(d[26]), "+f"(d[27]), "+f"(d[28]), "+f"(d[29]), "+f"(d[30]), "+f"(d[31]), "+f"(d[32]), "+f"(d[33]), "+f"(d[34]), "+f"(d[35]), "+f"(d[36]), "+f"(d[37]), "+f"(d[38]), "+f"(d[39]), "+f"(d[40]), "+f"(d[41]), "+f"(d[42]), "+f"(d[43]), "+f"(d[44]), "+f"(d[45]), "+f"(d[46]), "+f"(d[47]), "+f"(d[48]), "+f"(d[49]), "+f"(d[50]), "+f"(d[51]), "+f"(d[52]), "+f"(d[53]), "+f"(d[54]), "+f"(d[55])
    : "r"(a0), "r"(a1), "r"(a2), "r"(a3), "l"(b), "r"(sc)); } };
template<> struct WG<120> { static __device__ __forceinline__ void rs(float* d, uint32_t a0, uint32_t a1, uint32_t a2, uint32_t a3, uint64_t b, int sc) {
  asm volatile("{\n.reg .pred p;\nsetp.ne.b32 p, %65, 0;\nwgmma.mma_async.sync.aligned.m64n120k16.f32.bf16.bf16 {%0, %1, %2, %3, %4, %5, %6, %7, %8, %9, %10, %11, %12, %13, %14, %15, %16, %17, %18, %19, %20, %21, %22, %23, %24, %25, %26, %27, %28, %29, %30, %31, %32, %33, %34, %35, %36, %37, %38, %39, %40, %41, %42, %43, %44, %45, %46, %47, %48, %49, %50, %51, %52, %53, %54, %55, %56, %57, %58, %59}, {%60, %61, %62, %63}, %64, p, 1, 1, 0;\n}\n"
    : "+f"(d[0]), "+f"(d[1]), "+f"(d[2]), "+f"(d[3]), "+f"(d[4]), "+f"(d[5]), "+f"(d[6]), "+f"(d[7]), "+f"(d[8]), "+f"(d[9]), "+f"(d[10]), "+f"(d[11]), "+f"(d[12]), "+f"(d[13]), "+f"(d[14]), "+f"(d[15]), "+f"(d[16]), "+f"(d[17]), "+f"(d[18]), "+f"(d[19]), "+f"(d[20]), "+f"(d[21]), "+f"(d[22]), "+f"(d[23]), "+f"(d[24]), "+f"(d[25]), "+f"(d[26]), "+f"(d[27]), "+f"(d[28]), "+f"(d[29]), "+f"(d[30]), "+f"(d[31]), "+f"(d[32]), "+f"(d[33]), "+f"(d[34]), "+f"(d[35]), "+f"(d[36]), "+f"(d[37]), "+f"(d[38]), "+f"(d[39]), "+f"(d[40]), "+f"(d[41]), "+f"(d[42]), "+f"(d[43]), "+f"(d[44]), "+f"(d[45]), "+f"(d[46]), "+f"(d[47]), "+f"(d[48]), "+f"(d[49]), "+f"(d[50]), "+f"(d[51]), "+f"(d[52]), "+f"(d[53]), "+f"(d[54]), "+f"(d[55]), "+f"(d[56]), "+f"(d[57]), "+f"(d[58]), "+f"(d[59])
    : "r"(a0), "r"(a1), "r"(a2), "r"(a3), "l"(b), "r"(sc)); } };
template<> struct WG<128> { static __device__ __forceinline__ void rs(float* d, uint32_t a0, uint32_t a1, uint32_t a2, uint32_t a3, uint64_t b, int sc) {
  asm volatile("{\n.reg .pred p;\nsetp.ne.b32 p, %69, 0;\nwgmma.mma_async.sync.aligned.m64n128k16.f32.bf16.bf16 {%0, %1, %2, %3, %4, %5, %6, %7, %8, %9, %10, %11, %12, %13, %14, %15, %16, %17, %18, %19, %20, %21, %22, %23, %24, %25, %26, %27, %28, %29, %30, %31, %32, %33, %34, %35, %36, %37, %38, %39, %40, %41, %42, %43, %44, %45, %46, %47, %48, %49, %50, %51, %52, %53, %54, %55, %56, %57, %58, %59, %60, %61, %62, %63}, {%64, %65, %66, %67}, %68, p, 1, 1, 0;\n}\n"
    : "+f"(d[0]), "+f"(d[1]), "+f"(d[2]), "+f"(d[3]), "+f"(d[4]), "+f"(d[5]), "+f"(d[6]), "+f"(d[7]), "+f"(d[8]), "+f"(d[9]), "+f"(d[10]), "+f"(d[11]), "+f"(d[12]), "+f"(d[13]), "+f"(d[14]), "+f"(d[15]), "+f"(d[16]), "+f"(d[17]), "+f"(d[18]), "+f"(d[19]), "+f"(d[20]), "+f"(d[21]), "+f"(d[22]), "+f"(d[23]), "+f"(d[24]), "+f"(d[25]), "+f"(d[26]), "+f"(d[27]), "+f"(d[28]), "+f"(d[29]), "+f"(d[30]), "+f"(d[31]), "+f"(d[32]), "+f"(d[33]), "+f"(d[34]), "+f"(d[35]), "+f"(d[36]), "+f"(d[37]), "+f"(d[38]), "+f"(d[39]), "+f"(d[40]), "+f"(d[41]), "+f"(d[42]), "+f"(d[43]), "+f"(d[44]), "+f"(d[45]), "+f"(d[46]), "+f"(d[47]), "+f"(d[48]), "+f"(d[49]), "+f"(d[50]), "+f"(d[51]), "+f"(d[52]), "+f"(d[53]), "+f"(d[54]), "+f"(d[55]), "+f"(d[56]), "+f"(d[57]), "+f"(d[58]), "+f"(d[59]), "+f"(d[60]), "+f"(d[61]), "+f"(d[62]), "+f"(d[63])
    : "r"(a0), "r"(a1), "r"(a2), "r"(a3), "l"(b), "r"(sc)); } };

__device__ __forceinline__ uint32_t smem_u32(const void* p){ return (uint32_t)__cvta_generic_to_shared(p); }
__device__ __forceinline__ void wg_fence(){ asm volatile("wgmma.fence.sync.aligned;" ::: "memory"); }
__device__ __forceinline__ void wg_commit(){ asm volatile("wgmma.commit_group.sync.aligned;" ::: "memory"); }
template<int N> __device__ __forceinline__ void wg_wait(){ asm volatile("wgmma.wait_group.sync.aligned %0;" :: "n"(N) : "memory"); }
__device__ __forceinline__ uint32_t lds32(uint32_t a){ uint32_t v; asm volatile("ld.shared.u32 %0, [%1];" : "=r"(v) : "r"(a)); return v; }
__device__ __forceinline__ uint32_t mov32(uint32_t a){ uint32_t v; asm volatile("mov.b32 %0, %1;" : "=r"(v) : "r"(a)); return v; }
__device__ __forceinline__ float movf(float a){ float v; asm volatile("mov.f32 %0, %1;" : "=f"(v) : "f"(a)); return v; }
__device__ __forceinline__ void sts64(uint32_t a, float x, float y){ asm volatile("st.shared.v2.f32 [%0], {%1,%2};" :: "r"(a), "f"(x), "f"(y) : "memory"); }
__device__ __forceinline__ float rbf(float x){ return __bfloat162float(__float2bfloat16_rn(x)); }
__device__ __forceinline__ float bflo(uint32_t w){ return __uint_as_float(w << 16); }
__device__ __forceinline__ float bfhi(uint32_t w){ return __uint_as_float(w & 0xffff0000u); }
__device__ __forceinline__ uint32_t packbf(float lo, float hi){ __nv_bfloat162 t = __floats2bfloat162_rn(lo, hi); return *(uint32_t*)&t; }
__device__ __forceinline__ void bar_sync(int id, int n){ asm volatile("bar.sync %0, %1;" :: "r"(id), "r"(n) : "memory"); }
__device__ __forceinline__ void fence_async(){ asm volatile("fence.proxy.async.shared::cta;" ::: "memory"); }
__device__ __forceinline__ uint4 ldg_rlx(const void* p){ uint4 v; asm volatile("ld.relaxed.gpu.global.v4.u32 {%0,%1,%2,%3}, [%4];" : "=r"(v.x),"=r"(v.y),"=r"(v.z),"=r"(v.w) : "l"(p) : "memory"); return v; }
__device__ __forceinline__ uint2 ldg_rlx2(const void* p){ uint2 v; asm volatile("ld.relaxed.gpu.global.v2.u32 {%0,%1}, [%2];" : "=r"(v.x),"=r"(v.y) : "l"(p) : "memory"); return v; }
__device__ __forceinline__ void stg_rlx(void* p, uint4 v){ asm volatile("st.relaxed.gpu.global.v4.u32 [%0], {%1,%2,%3,%4};" :: "l"(p), "r"(v.x),"r"(v.y),"r"(v.z),"r"(v.w) : "memory"); }
__device__ __forceinline__ void stg_rlx2(void* p, uint2 v){ asm volatile("st.relaxed.gpu.global.v2.u32 [%0], {%1,%2};" :: "l"(p), "r"(v.x),"r"(v.y) : "memory"); }
__device__ __forceinline__ bool hz(uint32_t w){ return ((w - 0x00010001u) & ~w & 0x80008000u) != 0u; }
__device__ __forceinline__ bool valid16(uint4 v){ return !(hz(v.x) | hz(v.y) | hz(v.z) | hz(v.w)); }
__device__ __forceinline__ uint4 not4(uint4 v){ return make_uint4(~v.x, ~v.y, ~v.z, ~v.w); }
__device__ __forceinline__ void mb_init(uint32_t a, int cnt){ asm volatile("mbarrier.init.shared::cta.b64 [%0], %1;" :: "r"(a), "r"(cnt) : "memory"); }
__device__ __forceinline__ void mb_arrive(uint32_t a){ asm volatile("mbarrier.arrive.shared::cta.b64 _, [%0];" :: "r"(a) : "memory"); }
__device__ __forceinline__ void mb_expect(uint32_t a, uint32_t bytes){ asm volatile("mbarrier.arrive.expect_tx.shared::cta.b64 _, [%0], %1;" :: "r"(a), "r"(bytes) : "memory"); }
__device__ __forceinline__ void mb_wait(uint32_t a, uint32_t parity){
  uint32_t ok; int it = 0;
  do {
    asm volatile("{\n.reg .pred p;\nmbarrier.try_wait.parity.shared::cta.b64 p, [%1], %2;\nselp.u32 %0, 1, 0, p;\n}\n" : "=r"(ok) : "r"(a), "r"(parity) : "memory");
  } while(!ok && ++it < MB_SPIN_MAX);
}
__device__ __forceinline__ void bulk_g2s(uint32_t dst, const void* src, uint32_t bytes, uint32_t mb){
  asm volatile("cp.async.bulk.shared::cluster.global.mbarrier::complete_tx::bytes [%0], [%1], %2, [%3];" :: "r"(dst), "l"(src), "r"(bytes), "r"(mb) : "memory");
}
__device__ __forceinline__ uint32_t hmul2(uint32_t a, uint32_t b){ uint32_t d; asm("mul.rn.bf16x2 %0, %1, %2;" : "=r"(d) : "r"(a), "r"(b)); return d; }
__device__ __forceinline__ uint32_t hadd2(uint32_t a, uint32_t b){ uint32_t d; asm("add.rn.bf16x2 %0, %1, %2;" : "=r"(d) : "r"(a), "r"(b)); return d; }
__device__ __forceinline__ uint32_t hsub2(uint32_t a, uint32_t b){ uint32_t d; asm("sub.rn.bf16x2 %0, %1, %2;" : "=r"(d) : "r"(a), "r"(b)); return d; }
__device__ __forceinline__ uint32_t prmt(uint32_t a, uint32_t b, uint32_t sel){ return __byte_perm(a, b, sel); }

#define NREP 1
#define CD 0
#define PFM 1
#define WWG 2
#define XW 1
#define PACE 1400
#define OPACE 250
#define YD 500
#define CB 40
#define HB 64
constexpr int NFF = 96;
__device__ __align__(128) bf16  g_kvx[CH * NCTA * 2048];
__device__ __align__(128) bf16  g_zx[D_ * S_];
__device__ __align__(128) uint2 g_cand[8 * NCTA];
__device__ __align__(128) bf16  g_crow[NCTA * 2 * D_];
__device__ __align__(128) float g_yp[NFF * D_];
__device__ __align__(128) unsigned g_hint[10 * 4 * 32];

constexpr int ZP = 16;
constexpr int UPLANE = (128+ZP)*16;
constexpr int UBYTES = 2*UPLANE;
constexpr int KCOPY = 4160;
constexpr int CHBYTES = UBYTES + 2*KCOPY;
constexpr int RP = 72;
constexpr int REDBYTES = 4*16*RP*4;
constexpr int HP = 648;
constexpr int STG_K = 19*256, STG_PH = 35*256;
constexpr int OFF_RED = CH*CHBYTES;
constexpr int OFF_UNI = OFF_RED + 4*REDBYTES;
constexpr int OFF_WG  = OFF_UNI;
constexpr int OFF_WU  = OFF_UNI + D_*32;
constexpr int OFF_XS  = OFF_UNI + CH*STG_PH;
constexpr int OFF_WD  = OFF_XS + RPB*HP*2;
constexpr int OFF_MISC = OFF_WD + D_*32;
constexpr int OFF_MB   = OFF_MISC;
constexpr int OFF_STAT = OFF_MB + 256;
constexpr int OFF_WR   = OFF_STAT + 256;
constexpr int OFF_XSEL = OFF_WR + D_*2;
constexpr int OFF_PART = OFF_XSEL + D_*2 + 128;
constexpr int OFF_GU   = OFF_PART + 8*64*4;
constexpr int OFF_HSEL = OFF_GU + 128;
constexpr int SMEM_BYTES = OFF_HSEL + 128;
static_assert(SMEM_BYTES <= 232448-256, "smem");
static_assert(OFF_WU + D_*32 <= OFF_XS, "wu");
static_assert(OFF_WU % 128 == 0 && OFF_WG % 128 == 0, "align");
enum { MB_SSM=0, MB_W=5, MB_READY=6, MB_DONE=11, MB_P1=16, MB_XST=17, MB_SETUP=18, MB_KV=19, MB_X=24, MB_OUT=25, MB_WIN=26, MB_K14=27 };

constexpr int NPH = 8;
template<int J> __device__ __forceinline__ void loadA(uint32_t (&Q)[8], uint32_t kaddr){
  Q[0] = lds32(kaddr + 2*(128*J));
  Q[1] = lds32(kaddr + 2*(128*J + 8));
  Q[3] = lds32(kaddr + 2*(128*J + 16));
  Q[5] = lds32(kaddr + 2*(128*J + 24));
  Q[7] = lds32(kaddr + 2*(128*J + 32));
  Q[2] = mov32(Q[1]);
  Q[4] = mov32(Q[3]);
  Q[6] = mov32(Q[5]);
}
__device__ __forceinline__ void hint_post(int idx){
  #pragma unroll
  for(int r=0;r<NREP;r++) asm volatile("red.relaxed.gpu.global.add.u32 [%0], 1;" :: "l"(&g_hint[(idx*4+r)*32]) : "memory");
}
__device__ __forceinline__ unsigned hint_poll(int idx){
  unsigned v; asm volatile("ld.relaxed.gpu.global.u32 %0, [%1];" : "=r"(v) : "l"(&g_hint[(idx*4 + (blockIdx.x&(NREP-1)))*32]) : "memory"); return v;
}
__device__ __forceinline__ void hint_wait(int idx, bool active, unsigned v, int backoff){
  if(active){
    int it=0;
    while(v < (unsigned)NCTA && ++it < SPIN_MAX){ __nanosleep(backoff); v = hint_poll(idx); }
  }
  __syncwarp();
}
struct ConvCtx { uint32_t kaddr, raddr, raddr7, Dw; uint64_t drow0; const float* red; uint8_t* ubase; int t, barid; bool post0; };
template<int HALF> __device__ __forceinline__ void conv_epi(const ConvCtx& cx){
  const int a = cx.t>>1, bh = cx.t&1;
  const float* rpA = cx.red + a + (bh ? 5 : 15)*RP;
  const float* rpB = cx.red + a + (bh ? 13 : 15)*RP;
  float y[8];
  #pragma unroll
  for(int i=0;i<8;i++){
    const float* rp = (i<6 ? rpA : rpB) - i*RP;
    const float v0 = rp[0], v1 = rp[16*RP], v2 = rp[32*RP], v3 = rp[48*RP];
    if(HALF==0) y[i] = (v0 + (a>=2 ? v1 : 0.f)) + ((a>=4 ? v2 : 0.f) + (a>=6 ? v3 : 0.f));
    else        y[i] = (v0 + v1) + (v2 + v3);
  }
  const uint4 u = *(const uint4*)(cx.ubase + bh*UPLANE + (ZP + 64*HALF + a)*16);
  const uint32_t p0 = packbf(y[0],y[1]), p1 = packbf(y[2],y[3]), p2 = packbf(y[4],y[5]), p3 = packbf(y[6],y[7]);
  uint4 z;
  z.x = hadd2(bh ? p3 : p0, hmul2(u.x, cx.Dw)); z.y = hadd2(bh ? p0 : p1, hmul2(u.y, cx.Dw));
  z.z = hadd2(bh ? p1 : p2, hmul2(u.z, cx.Dw)); z.w = hadd2(bh ? p2 : p3, hmul2(u.w, cx.Dw));
  *(uint4*)(cx.ubase + UBYTES + (128*HALF + cx.t)*16) = z;
  fence_async();
}
template<int P> struct Phase {
  static constexpr int J0 = 2*P, NP = 128-16*P;
  static __device__ __forceinline__ void run(float (&acc)[NP/2], float (&old)[8], uint32_t (&A)[2][8], const ConvCtx& cx){
    wg_fence();
    #pragma unroll
    for(int jj=0;jj<2;jj++){
      WG<NP>::rs(acc, A[jj][0], A[jj][1], A[jj][2], A[jj][3], cx.drow0 - (uint64_t)(8*jj), (P>0||jj>0)?1:0);
      WG<NP>::rs(acc, A[jj][4], A[jj][5], A[jj][6], A[jj][7], cx.drow0 - (uint64_t)(8*jj+1), 1);
    }
    wg_commit();
    if constexpr (P==5){
      bar_sync(cx.barid, 128);
      conv_epi<0>(cx);
      bar_sync(cx.barid, 128);
    }
    if constexpr (P==1){ if(cx.post0){ asm volatile("cp.async.bulk.wait_group 0;" ::: "memory"); hint_post(5); } }
    if constexpr (P>0) retire<J0-2>(old, cx);
    if constexpr (P+1 < NPH) {
      uint32_t B[2][8];
      loadA<J0+2>(B[0], cx.kaddr); loadA<J0+3>(B[1], cx.kaddr);
      wg_wait<0>();
      float nacc[NP/2 - 8];
      float nold[8];
      #pragma unroll
      for(int i=0;i<NP/2-8;i++) nacc[i] = movf(acc[8+i]);
      #pragma unroll
      for(int i=0;i<8;i++) nold[i] = movf(acc[i]);
      Phase<P+1>::run(nacc, nold, B, cx);
    } else {
      wg_wait<0>();
      float nold[8];
      #pragma unroll
      for(int i=0;i<8;i++) nold[i] = acc[i];
      retire<J0>(nold, cx);
    }
  }
  template<int JB> static __device__ __forceinline__ void retire(float (&o)[8], const ConvCtx& cx){
    #pragma unroll
    for(int jj=0;jj<2;jj++){
      const int jt = JB+jj;
      const uint32_t ad = (jt==7 ? cx.raddr7 : cx.raddr) + 4*8*(jt&7);
      sts64(ad, o[4*jj], o[4*jj+1]);
      sts64(ad + 4*8*RP, o[4*jj+2], o[4*jj+3]);
    }
  }
};

__device__ __forceinline__ void mb_wait_slow(uint32_t a, uint32_t parity){
  uint32_t ok; int it = 0;
  while(true){
    asm volatile("{\n.reg .pred p;\nmbarrier.try_wait.parity.shared::cta.b64 p, [%1], %2;\nselp.u32 %0, 1, 0, p;\n}\n" : "=r"(ok) : "r"(a), "r"(parity) : "memory");
    if(ok || ++it >= MB_SPIN_MAX) break;
    __nanosleep(100);
  }
}
__device__ __forceinline__ void tma2d(uint32_t dst, const CUtensorMap* tm, int c0, int c1, uint32_t mb){
  asm volatile("cp.async.bulk.tensor.2d.shared::cluster.global.mbarrier::complete_tx::bytes [%0], [%1, {%3, %4}], [%2];" :: "r"(dst), "l"((uint64_t)tm), "r"(mb), "r"(c0), "r"(c1) : "memory");
}
__device__ __forceinline__ void l2_prefetch(const void* src, uint32_t bytes){
  asm volatile("cp.async.bulk.prefetch.L2.global [%0], %1;" :: "l"(src), "r"(bytes) : "memory");
}
__device__ __forceinline__ void bulk_s2g(void* dst, uint32_t src, uint32_t bytes){
  asm volatile("cp.async.bulk.global.shared::cta.bulk_group [%0], [%1], %2;" :: "l"(dst), "r"(src), "r"(bytes) : "memory");
}

__device__ __forceinline__ void conv_channel(uint8_t* sm, int c, int wg, int t, const bf16* __restrict__ ssm_D){
  const int w = t/32, lane = t%32, g = lane/4, cq = lane%4;
  uint8_t* base = sm + c*CHBYTES;
  const int ch = c*NCTA + blockIdx.x;
  ConvCtx cx;
  cx.Dw = (uint32_t)__ldg((const unsigned short*)(ssm_D + ch)) * 0x00010001u;
  const uint32_t ua = smem_u32(base);
  cx.drow0 = ((uint64_t)(UPLANE>>4) << 16) | ((uint64_t)(128>>4) << 32) | (uint64_t)(((ua+16*ZP)&0x3FFFF)>>4);
  const int xp = 32*w + g + 2*cq + 1;
  cx.kaddr = (xp&1) ? ua+UBYTES+KCOPY + 2*(xp-1) : ua+UBYTES + 2*xp;
  cx.red = (const float*)(sm + OFF_RED + wg*REDBYTES);
  cx.raddr = smem_u32(cx.red) + 4*((w*16+g)*RP + 2*cq + 2*w);
  cx.raddr7 = cx.raddr - ((w+cq>=4) ? 256 : 0);
  cx.ubase = base; cx.t = t; cx.barid = wg+1; cx.post0 = (c==4 && t==64);
  {
    float acc[64]; float old[8];
    uint32_t A[2][8];
    loadA<0>(A[0], cx.kaddr); loadA<1>(A[1], cx.kaddr);
    Phase<0>::run(acc, old, A, cx);
  }
  bar_sync(wg+1, 128);
  conv_epi<1>(cx);
  bar_sync(wg+1, 128);
  if(t==64){
    bulk_s2g(g_zx + (size_t)ch*S_, ua + UBYTES, 4096);
    asm volatile("cp.async.bulk.commit_group;" ::: "memory");
    if(c>0){ asm volatile("cp.async.bulk.wait_group 0;" ::: "memory"); hint_post(5+c); }
  }
}

template<int NTH> __device__ __forceinline__ void build_k1(uint8_t* sm, int c, int t){
  uint8_t* base = sm + c*CHBYTES;
  mb_wait(smem_u32(sm+OFF_MB) + 8*(MB_SSM+c), 0);
  const uint32_t* K0 = (const uint32_t*)(base+UBYTES);
  uint32_t* K1 = (uint32_t*)(base+UBYTES+KCOPY);
  #pragma unroll
  for(int r=0;r<(256/NTH)+1;r++){
    int i = t + NTH*r;
    if(i < 259){
      uint4 w = *(const uint4*)(K0+4*i);
      uint32_t nx = K0[4*i+4];
      *(uint4*)(K1+4*i) = make_uint4(__funnelshift_r(w.x,w.y,16), __funnelshift_r(w.y,w.z,16), __funnelshift_r(w.z,w.w,16), __funnelshift_r(w.w,nx,16));
    }
  }
}
__device__ __forceinline__ void load_row10(const bf16* row, int lane, uint32_t (&w)[10]){
  uint4 a = *(const uint4*)(row + 8*lane);
  uint4 b = *(const uint4*)(row + 256 + 8*lane);
  uint2 c = *(const uint2*)(row + 512 + 4*lane);
  w[0]=a.x; w[1]=a.y; w[2]=a.z; w[3]=a.w; w[4]=b.x; w[5]=b.y; w[6]=b.z; w[7]=b.w; w[8]=c.x; w[9]=c.y;
}
template<bool INV> __device__ __forceinline__ void store_row10(bf16* row, int lane, const uint32_t (&w)[10]){
  if(INV){
    stg_rlx(row + 8*lane, make_uint4(~w[0],~w[1],~w[2],~w[3]));
    stg_rlx(row + 256 + 8*lane, make_uint4(~w[4],~w[5],~w[6],~w[7]));
    stg_rlx2(row + 512 + 4*lane, make_uint2(~w[8],~w[9]));
  } else {
    *(uint4*)(row + 8*lane) = make_uint4(w[0],w[1],w[2],w[3]);
    *(uint4*)(row + 256 + 8*lane) = make_uint4(w[4],w[5],w[6],w[7]);
    *(uint2*)(row + 512 + 4*lane) = make_uint2(w[8],w[9]);
  }
}
__device__ __forceinline__ void ln_finish(float piv, float s, float q, float& mb, float& rinv){
  const float dm = s * (1.0f/D_);
  const float var = rbf(fmaxf(fmaf(-dm, dm, q * (1.0f/D_)), 0.f));
  mb = rbf(piv + dm);
  rinv = __frcp_rn(rbf(__fsqrt_rn(rbf(var + 1e-5f))));
}
__device__ __forceinline__ uint32_t ln_apply2(uint32_t x2, uint32_t mb2, float rlo, float rhi){
  uint32_t d = hsub2(x2, mb2);
  return packbf(bflo(d)*rlo, bfhi(d)*rhi);
}

struct MergeItem { uint32_t x2[4], q2[4]; };
__device__ __forceinline__ void merge_prep(const uint8_t* sm, int ch, int half, MergeItem& m){
  const unsigned short* mb = (const unsigned short*)(sm + OFF_STAT);
  const float* ri = (const float*)(sm + OFF_STAT + 64);
  const unsigned short* xs = (const unsigned short*)(sm + OFF_XS) + ch;
  #pragma unroll
  for(int i=0;i<4;i++){
    const int r1 = 15 - 8*half - 2*((i + 2*half)&3);
    m.x2[i] = (uint32_t)xs[r1*HP] | ((uint32_t)xs[(r1-1)*HP] << 16);
    const uint32_t mm = *(const uint32_t*)(mb + r1 - 1);
    const float2 rr = *(const float2*)(ri + r1 - 1);
    m.q2[i] = ln_apply2(m.x2[i], prmt(mm, mm, 0x1032), rr.y, rr.x);
  }
}
__device__ __forceinline__ void merge_fin(uint8_t* sm, int ch, int half, const MergeItem& m, uint4 z){
  unsigned short* xs = (unsigned short*)(sm + OFF_XS) + ch;
  if(half) z = make_uint4(z.z, z.w, z.x, z.y);
  const uint32_t zw[4] = {z.x,z.y,z.z,z.w};
  #pragma unroll
  for(int i=0;i<4;i++){
    const int r1 = 15 - 8*half - 2*((i + 2*half)&3);
    const uint32_t h2 = hadd2(m.x2[i], hmul2(m.q2[i], zw[i]));
    xs[r1*HP] = (unsigned short)h2; xs[(r1-1)*HP] = (unsigned short)(h2>>16);
  }
}
#define MMA16816(C,A0,A1,A2,A3,B0,B1) asm volatile("mma.sync.aligned.m16n8k16.row.col.f32.bf16.bf16.f32 {%0,%1,%2,%3}, {%4,%5,%6,%7}, {%8,%9}, {%0,%1,%2,%3};" \
   : "+f"(C[0]),"+f"(C[1]),"+f"(C[2]),"+f"(C[3]) : "r"(A0),"r"(A1),"r"(A2),"r"(A3),"r"(B0),"r"(B1))

__global__ void __launch_bounds__(NT, 1) fused_kernel(const bf16* __restrict__ x, const __grid_constant__ CUtensorMap tm_k, const __grid_constant__ CUtensorMap tm_v,
    const bf16* __restrict__ shift_k, const bf16* __restrict__ ssm_k, const bf16* __restrict__ ssm_D, const bf16* __restrict__ w_r,
    const __grid_constant__ CUtensorMap tm_kvx, const __grid_constant__ CUtensorMap tm_gate, const __grid_constant__ CUtensorMap tm_up,
    const bf16* __restrict__ w_gate, const bf16* __restrict__ w_up, const bf16* __restrict__ w_down, bf16* __restrict__ out)
{
  extern __shared__ __align__(1024) uint8_t sm[];
  const int tid = threadIdx.x, wg = tid>>7, t = tid&127, warp = tid>>5, lane = tid&31, wq = warp&3;
  const int b = blockIdx.x, s0 = b*RPB;
  const uint32_t mbase = smem_u32(sm + OFF_MB);
  const uint4 z4 = make_uint4(0,0,0,0);

  const long long tb = clock64();
  auto issue_phase = [&](int j){
    const uint32_t stg = smem_u32(sm + OFF_UNI + j*STG_PH);
    mb_expect(mbase+8*(MB_KV+j), STG_PH);
    tma2d(stg, &tm_k, j*128, s0-3, mbase+8*(MB_KV+j));
    tma2d(stg + STG_K, &tm_v, j*128, s0, mbase+8*(MB_KV+j));
  };
  auto issue_ssm = [&](int j){
    mb_expect(mbase+8*(MB_SSM+j), 4096);
    bulk_g2s(smem_u32(sm + j*CHBYTES + UBYTES + 32), ssm_k + (size_t)(j*NCTA+b)*S_, 4096, mbase+8*(MB_SSM+j));
  };
  if(tid==96){
    #pragma unroll
    for(int i=0;i<5;i++){ mb_init(mbase+8*(MB_KV+i),1); mb_init(mbase+8*(MB_SSM+i),1); mb_init(mbase+8*(MB_READY+i),1); }
    mb_init(mbase+8*MB_W,3); mb_init(mbase+8*MB_XST,128); mb_init(mbase+8*MB_P1,5); mb_init(mbase+8*MB_SETUP,128); mb_init(mbase+8*MB_X,1); mb_init(mbase+8*MB_OUT,512); mb_init(mbase+8*MB_WIN,32); mb_init(mbase+8*MB_K14,96);
    asm volatile("fence.mbarrier_init.release.cluster;" ::: "memory");
    fence_async();
    issue_phase(0);
  }
  unsigned hv = 0;
  if(wq==3 && lane<10 && ((wg==0 ? 0x001u : wg==1 ? 0x3A2u : wg==2 ? 0x044u : 0x018u) >> lane & 1u)) hv = hint_poll(lane);
  const uint4 skA = __ldg((const uint4*)(shift_k + (size_t)(wg*128 + 2*(t&63))*4));
  const uint4 skB = __ldg((const uint4*)(shift_k + (size_t)(512 + 2*(t&63))*4));
  __syncthreads();
  if(wg==3){
    if(t==64){ asm volatile("prefetch.tensormap [%0];" :: "l"((uint64_t)&tm_kvx) : "memory"); asm volatile("prefetch.tensormap [%0];" :: "l"((uint64_t)&tm_gate) : "memory"); asm volatile("prefetch.tensormap [%0];" :: "l"((uint64_t)&tm_up) : "memory"); }
    #pragma unroll
    for(int i=0;i<2;i++){
      const int u = t + 128*i;
      if(u<160){ ((uint4*)g_crow)[b*160 + u] = z4; if(b<NFF) ((uint4*)g_yp)[b*160 + u] = z4; }
      else if(u<168) g_cand[(u-160)*NCTA + b] = make_uint2(0u,0u);
      if(u<180){
        int c = u/36, r = u%36;
        uint8_t* base = sm + c*CHBYTES;
        uint8_t* p = (r<32) ? base + (r>>4)*UPLANE + (r&15)*16 : base + UBYTES + (r<34 ? (r-32)*16 : 4128 + (r-34)*16);
        *(uint4*)p = z4;
      }
    }
    if(t<80) *(uint4*)(sm + OFF_WR + t*16) = __ldg((const uint4*)w_r + t);
    fence_async();
    mb_arrive(mbase+8*MB_SETUP);
  }
  if(t==96){
    if(wg>0){ while(clock64() - tb < (long long)wg*PACE) ; issue_phase(wg); }
    while(clock64() - tb < (long long)wg*PACE + (PACE*2)/3) ;
    issue_ssm(wg);
    if(wg==3){
      while(clock64() - tb < (long long)4*PACE) ;
      issue_phase(4);
      while(clock64() - tb < (long long)4*PACE + (PACE*2)/3) ;
      issue_ssm(4);
    }
  }
  __syncwarp();
  {
    const int np = (wg==3) ? 2 : 1;
    const int cp = t&63, hf = t>>6;
    #pragma unroll 1
    for(int i=0;i<np;i++){
      const int pj = wg+i;
      const uint8_t* stg = sm + OFF_UNI + pj*STG_PH;
      const uint4 sk = i ? skB : skA;
      mb_wait(mbase+8*(MB_KV+pj), 0);
      const uint32_t s0w = prmt(sk.x, sk.z, 0x5410), s1w = prmt(sk.x, sk.z, 0x7632), s2w = prmt(sk.y, sk.w, 0x5410), s3w = prmt(sk.y, sk.w, 0x7632);
      const uint32_t* kA = (const uint32_t*)stg + (hf ? 0 : 512) + cp;
      const uint32_t* vs = (const uint32_t*)(stg + STG_K) + (hf ? 0 : 512) + cp;
      uint32_t kk[11], o[8];
      #pragma unroll
      for(int r=0;r<11;r++) kk[r] = kA[r*64];
      #pragma unroll
      for(int r=0;r<8;r++){
        uint32_t a = hadd2(hmul2(kk[r], s3w), hmul2(kk[r+1], s2w));
        a = hadd2(a, hmul2(kk[r+2], s1w));
        a = hadd2(a, hmul2(kk[r+3], s0w));
        o[r] = hmul2(a, vs[r*64]);
      }
      bar_sync(wg+1, 128);
      uint4* sd = (uint4*)(sm + OFF_UNI + pj*STG_PH) + 2*cp + hf;
      sd[0]   = make_uint4(prmt(o[7],o[6],0x5410), prmt(o[5],o[4],0x5410), prmt(o[3],o[2],0x5410), prmt(o[1],o[0],0x5410));
      sd[128] = make_uint4(prmt(o[7],o[6],0x7632), prmt(o[5],o[4],0x7632), prmt(o[3],o[2],0x7632), prmt(o[1],o[0],0x7632));
      fence_async();
      bar_sync(wg+1, 128);
      if(t==64){
        bulk_s2g(g_kvx + (size_t)(pj*NCTA + b)*2048, smem_u32(stg), 4096);
        asm volatile("cp.async.bulk.commit_group;" ::: "memory");
        asm volatile("cp.async.bulk.wait_group 0;" ::: "memory");
        hint_post(pj);
        mb_arrive(mbase+8*MB_P1);
      }
    }
  }
  bf16* const zx = g_zx;
  mb_wait(mbase+8*MB_SETUP, 0);
  if(wq==3){
    #pragma unroll 1
    for(int c=wg; c<(wg==3 ? 5 : wg+1); c++){
      if(lane==c){
        unsigned v = hv; int it=0;
        while(v < (unsigned)NCTA && ++it < SPIN_MAX){ __nanosleep(HB); v = hint_poll(lane); }
        const uint32_t dst = smem_u32(sm + lane*CHBYTES + ZP*16), mb = mbase+8*(MB_READY+lane);
        mb_expect(mb, 4096);
        tma2d(dst, &tm_kvx, (b&1)*1024 + (b>>1)*16, lane*NCTA, mb);
        tma2d(dst + UPLANE, &tm_kvx, (b&1)*1024 + (b>>1)*16 + 8, lane*NCTA, mb);
      }
      __syncwarp();
    }
  } else {
    build_k1<96>(sm, wg, t);
    if(wg==3){
      build_k1<96>(sm, 4, t);
      mb_arrive(mbase+8*MB_K14);
      if(wq==XW){
        if(lane==0) mb_expect(mbase+8*MB_X, RPB*D_*2);
        __syncwarp();
        if(lane<RPB) bulk_g2s(smem_u32(sm + OFF_XS + lane*(HP*2)), x + (size_t)(s0+lane)*D_, D_*2, mbase+8*MB_X);
        __syncwarp();
      }
    }
    if(t==0) mb_wait(mbase+8*(MB_READY+wg), 0);
  }
  bar_sync(wg+1, 128);
  #pragma unroll 1
  for(int c=wg; c<CH; c+=4){
    if(c==4){ if(t==0){ mb_wait(mbase+8*(MB_READY+4), 0); mb_wait(mbase+8*MB_K14, 0); } bar_sync(1, 128); }
    conv_channel(sm, c, wg, t, ssm_D);
    if(t==0 && c<3) l2_prefetch((c==0 ? w_gate : c==1 ? w_up : w_down) + (size_t)b*(D_*F_/NCTA), D_*F_/NCTA*2);
  }
  if(wg==1){
    mb_wait(mbase+8*MB_X, 0);
    {
      const uint4* xp = (const uint4*)(sm + OFF_XS + (t>>3)*(HP*2));
      const float piv = bflo(*(const uint32_t*)xp);
      float s0a=0, s1a=0, q0=0, q1=0;
      #pragma unroll
      for(int i=0;i<10;i++){
        const uint4 w = xp[(t&7) + 8*i];
        const uint32_t w4[4] = {w.x, w.y, w.z, w.w};
        #pragma unroll
        for(int e=0;e<4;e++){ float a=bflo(w4[e])-piv, c=bfhi(w4[e])-piv; s0a+=a; s1a+=c; q0=fmaf(a,a,q0); q1=fmaf(c,c,q1); }
      }
      float ss=s0a+s1a, qq=q0+q1;
      #pragma unroll
      for(int o=4;o>0;o>>=1){ ss += __shfl_xor_sync(0xffffffffu, ss, o); qq += __shfl_xor_sync(0xffffffffu, qq, o); }
      float mb, ri; ln_finish(piv, ss, qq, mb, ri);
      if((t&7)==0){ ((unsigned short*)(sm+OFF_STAT))[t>>3] = (unsigned short)(__float_as_uint(mb)>>16); ((float*)(sm+OFF_STAT+64))[t>>3] = ri; }
    }
    mb_arrive(mbase+8*MB_XST);
  }
  if(wg==WWG && t==32 && b<NFF){
    mb_wait(mbase+8*MB_P1, 0);
    fence_async();
    mb_expect(mbase+8*MB_W, D_*32);
    #pragma unroll 1
    for(int q=0;q<5;q++) tma2d(smem_u32(sm + OFF_WG + q*4096), &tm_gate, b*16, q*128, mbase+8*MB_W);
    mb_expect(mbase+8*MB_W, D_*32);
    #pragma unroll 1
    for(int q=0;q<5;q++) tma2d(smem_u32(sm + OFF_WU + q*4096), &tm_up, b*16, q*128, mbase+8*MB_W);
    mb_expect(mbase+8*MB_W, 16*D_*2);
    bulk_g2s(smem_u32(sm + OFF_WD), w_down + (size_t)b*16*D_, 16*D_*2, mbase+8*MB_W);
  }
  if(wg==2 && wq==0){
    uint32_t wr[10]; load_row10((const bf16*)(sm + OFF_WR), lane, wr);
    float sw=0;
    #pragma unroll
    for(int i=0;i<10;i++) sw += bflo(wr[i]) + bfhi(wr[i]);
    #pragma unroll
    for(int o=16;o>0;o>>=1) sw += __shfl_xor_sync(0xffffffffu, sw, o);
    if(lane==0) *(float*)(sm + OFF_GU + 68) = sw;
  }
  if(wg!=1){ if(t==0) mb_wait_slow(mbase+8*MB_XST, 0); }
  bar_sync(wg+1, 128);
  if(wg==1 || wg==2){
    const int c0 = (wg-1)*128 + (t>>1);
    MergeItem m0, m1; merge_prep(sm, c0, t&1, m0); merge_prep(sm, c0+64, t&1, m1);
    if(wq==3) hint_wait(lane, lane==4+wg, hv, 100);
    bar_sync(wg+1, 128);
    const bf16* p0 = zx + (size_t)c0*S_ + s0 + 8*(t&1);
    const uint4 a0 = ldg_rlx(p0), a1 = ldg_rlx(p0 + (size_t)64*S_);
    merge_fin(sm, c0, t&1, m0, a0); merge_fin(sm, c0+64, t&1, m1, a1);
    if(wg==1 && wq==3){ hint_wait(lane, lane>=7 && lane<=9, hv, HB); }
  }
  {
    const int ch = 256 + (tid>>1);
    MergeItem m0, m1; merge_prep(sm, ch, tid&1, m0);
    if(tid<256) merge_prep(sm, ch+256, tid&1, m1);
    __syncthreads();
    const bf16* p0 = zx + (size_t)ch*S_ + s0 + 8*(tid&1);
    const uint4 a0 = ldg_rlx(p0);
    if(tid<256){ const uint4 a1 = ldg_rlx(p0 + (size_t)256*S_); merge_fin(sm, ch+256, tid&1, m1, a1); }
    merge_fin(sm, ch, tid&1, m0, a0);
  }
  __syncthreads();
  float* part = (float*)(sm + OFF_PART);
  if(warp<8){
    float c0[4]={0,0,0,0}, c1[4]={0,0,0,0}, c2[4]={0,0,0,0};
    const uint32_t ha = smem_u32(sm + OFF_XS) + (lane&15)*(HP*2) + (lane>>4)*16 + warp*160;
    const uint32_t* wp = (const uint32_t*)(sm + OFF_WR) + warp*40 + (lane&3);
    const int g = lane>>2;
    #pragma unroll
    for(int ks=0;ks<5;ks++){
      uint32_t a0,a1,a2,a3;
      asm volatile("ldmatrix.sync.aligned.m8n8.x4.shared.b16 {%0,%1,%2,%3}, [%4];" : "=r"(a0),"=r"(a1),"=r"(a2),"=r"(a3) : "r"(ha + ks*32));
      uint32_t b0 = (g==0) ? 0x3f803f80u : 0u, b1 = b0;
      if(g==1){ b0 = wp[ks*8]; b1 = wp[ks*8+4]; }
      MMA16816(c0,a0,a1,a2,a3,a0,a2); MMA16816(c1,a0,a1,a2,a3,a1,a3); MMA16816(c2,a0,a1,a2,a3,b0,b1);
    }
    float* pw = part + warp*64;
    if((lane&3)==(g>>1)){ pw[g*4] = (g&1) ? c0[1] : c0[0]; pw[(g+8)*4] = (g&1) ? c1[3] : c1[2]; }
    if((lane&3)==0){ *(float2*)(pw + g*4 + 2) = make_float2(c2[0], c2[1]); *(float2*)(pw + (g+8)*4 + 2) = make_float2(c2[2], c2[3]); }
    asm volatile("bar.sync 12, 256;" ::: "memory");
    if(warp==0){
      float q=0, sh=0, shw=0;
      #pragma unroll
      for(int i=0;i<8;i++){ float4 p4 = *(const float4*)(part + i*64 + (lane&15)*4); q += p4.x; sh += p4.z; shw += p4.w; }
      float mb, ri; ln_finish(0.f, sh, q, mb, ri);
      float br = rbf(fmaf(-mb, *(const float*)(sm + OFF_GU + 68), shw) * ri);
      if(lane<16){ ((float*)(sm+OFF_STAT+128))[lane] = mb; ((float*)(sm+OFF_STAT+192))[lane] = ri; }
      int best = lane&15;
      #pragma unroll
      for(int o=8;o>0;o>>=1){
        float r2 = __shfl_xor_sync(0xffffffffu, br, o); int i2 = __shfl_xor_sync(0xffffffffu, best, o);
        if(r2>br || (r2==br && i2<best)){ br=r2; best=i2; }
      }
      if(lane<8) stg_rlx2(&g_cand[lane*NCTA + b], make_uint2(~__float_as_uint(br), (unsigned)(s0+best+1)));
      if(lane==0) *(volatile int*)(sm + OFF_GU + 72) = best;
    }
  }
  uint32_t h[10];
  load_row10((const bf16*)(sm+OFF_XS) + warp*HP, lane, h);
  __syncthreads();
  const int best = *(volatile int*)(sm + OFF_GU + 72);
  {
    const float mb = ((const float*)(sm+OFF_STAT+128))[warp], ri = ((const float*)(sm+OFF_STAT+192))[warp];
    const uint32_t mb2 = (__float_as_uint(mb)>>16) * 0x00010001u;
    uint32_t xn[10];
    #pragma unroll
    for(int i=0;i<10;i++) xn[i] = ln_apply2(h[i], mb2, ri, ri);
    if(warp==best){
      store_row10<true>(g_crow + (size_t)b*2*D_, lane, xn);
      store_row10<true>(g_crow + (size_t)b*2*D_ + D_, lane, h);
    }
    #pragma unroll
    for(int i=0;i<10;i++) h[i] = hadd2(h[i], xn[i]);
    store_row10<false>((bf16*)(sm+OFF_XS) + warp*HP, lane, h);
    fence_async();
    mb_arrive(mbase+8*MB_OUT);
  }
  float* cr = (float*)(sm + OFF_HSEL + 32);
  int* ci = (int*)(sm + OFF_HSEL + 48);
  if(warp==14){
    if(lane==0){
      mb_wait(mbase+8*MB_OUT, 0);
      const long long t0 = clock64();
      #pragma unroll 1
      for(int r=0;r<RPB;r++){
        if(r != best) bulk_s2g(out + (size_t)(s0+r)*D_, smem_u32(sm + OFF_XS + r*(HP*2)), D_*2);
        while(clock64() - t0 < (long long)(r+1)*OPACE) ;
      }
      asm volatile("cp.async.bulk.commit_group;" ::: "memory");
      asm volatile("cp.async.bulk.wait_group.read 0;" ::: "memory");
    }
    return;
  }
  if(warp==15){
    const uint4* cp4 = (const uint4*)(g_cand + (b&7)*NCTA) + lane;
    const bool third = lane<16 || (lane<18 && b<40);
    const int o3 = lane<16 ? 64+lane : 80 + b*2 + (lane-16);
    uint4 a0 = z4, a1 = z4, a2 = make_uint4(0x00010001u,0x00010001u,0x00010001u,0x00010001u);
    int spec = -1, it = 0; float r; int idx;
    __nanosleep(CD);
    while(true){
      const uint4 c0 = ldg_rlx(cp4), c1 = ldg_rlx(cp4+32);
      const uint32_t cx[4] = {c0.x, c0.z, c1.x, c1.z}, cy[4] = {c0.y, c0.w, c1.y, c1.w};
      r = -INFINITY; idx = 0x7fffffff; bool ok = true;
      #pragma unroll
      for(int i=0;i<4;i++){
        const bool v = cx[i]!=0u && cy[i]!=0u; ok &= v;
        const float r2 = __uint_as_float(~cx[i]);
        if(v && (r2>r || idx==0x7fffffff)){ r=r2; idx=(int)cy[i]-1; }
      }
      #pragma unroll
      for(int o2=16;o2>0;o2>>=1){
        float r2 = __shfl_xor_sync(0xffffffffu, r, o2); int i2 = __shfl_xor_sync(0xffffffffu, idx, o2);
        if(r2>r || (!(r2<r) && i2<idx)){ r=r2; idx=i2; }
      }
      idx = __shfl_sync(0xffffffffu, idx, 0); r = __shfl_sync(0xffffffffu, r, 0);
      const bool all = __all_sync(0xffffffffu, ok) || ++it>=SPIN_MAX;
      idx = min(idx, S_-1);
      if(b<NFF && (idx>>4)!=spec){
        spec = idx>>4;
        const uint4* wr4 = (const uint4*)(g_crow + (size_t)spec*2*D_);
        a0 = ldg_rlx(wr4+lane); a1 = ldg_rlx(wr4+32+lane); if(third) a2 = ldg_rlx(wr4+o3);
      }
      if(all) break;
      __nanosleep(CB);
    }
    if(b<NFF){
      const uint4* wr4 = (const uint4*)(g_crow + (size_t)spec*2*D_);
      it = 0;
      while(!(valid16(a0) && valid16(a1) && valid16(a2)) && ++it<SPIN_MAX){ a0 = ldg_rlx(wr4+lane); a1 = ldg_rlx(wr4+32+lane); if(third) a2 = ldg_rlx(wr4+o3); }
      uint4* xd = (uint4*)(sm + OFF_XSEL);
      xd[lane] = not4(a0); xd[32+lane] = not4(a1); if(third) xd[64+lane] = not4(a2);
    }
    if(lane==0){ cr[0]=r; ci[0]=idx; }
    mb_arrive(mbase+8*MB_WIN);
    if(lane==0){
      if(s0+best != idx){
        mb_wait(mbase+8*MB_OUT, 0);
        bulk_s2g(out + (size_t)(s0+best)*D_, smem_u32(sm + OFF_XS + best*(HP*2)), D_*2);
        asm volatile("cp.async.bulk.commit_group;" ::: "memory");
      }
    }
  }
  if(warp>=12) goto done;
  mb_wait(mbase+8*MB_WIN, 0);
  {
  const float wrr = cr[0]; const int widx = ci[0];
  if(b==0 && tid>=320 && tid<360) g_hint[(tid-320)*32] = 0u;
  if(b<NFF){
    if(warp<8){
      uint32_t xa[10];
      const uint32_t* xp = (const uint32_t*)(sm + OFF_XSEL) + warp*40 + (lane&3);
      #pragma unroll
      for(int i=0;i<10;i++) xa[i] = lane<4 ? xp[4*i] : 0u;
      mb_wait(mbase+8*MB_W, 0);
      __syncwarp();
      float c0[4]={0,0,0,0}, c1[4]={0,0,0,0}, c2[4]={0,0,0,0}, c3[4]={0,0,0,0};
      const uint32_t wo = (warp*80 + (lane&15))*32 + (lane>>4)*16;
      const uint32_t ga = smem_u32(sm + OFF_WG) + wo, ua = smem_u32(sm + OFF_WU) + wo;
      #pragma unroll
      for(int ks=0;ks<5;ks++){
        uint32_t b0,b1,b2,b3,b4,b5,b6,b7;
        asm volatile("ldmatrix.sync.aligned.m8n8.x4.trans.shared.b16 {%0,%1,%2,%3}, [%4];" : "=r"(b0),"=r"(b1),"=r"(b2),"=r"(b3) : "r"(ga + ks*512));
        asm volatile("ldmatrix.sync.aligned.m8n8.x4.trans.shared.b16 {%0,%1,%2,%3}, [%4];" : "=r"(b4),"=r"(b5),"=r"(b6),"=r"(b7) : "r"(ua + ks*512));
        MMA16816(c0,xa[2*ks],0u,xa[2*ks+1],0u,b0,b1); MMA16816(c1,xa[2*ks],0u,xa[2*ks+1],0u,b2,b3);
        MMA16816(c2,xa[2*ks],0u,xa[2*ks+1],0u,b4,b5); MMA16816(c3,xa[2*ks],0u,xa[2*ks+1],0u,b6,b7);
      }
      if(lane<4){
        *(float2*)(part + warp*32 + 2*lane) = make_float2(c0[0],c0[1]);
        *(float2*)(part + warp*32 + 8 + 2*lane) = make_float2(c1[0],c1[1]);
        *(float2*)(part + warp*32 + 16 + 2*lane) = make_float2(c2[0],c2[1]);
        *(float2*)(part + warp*32 + 24 + 2*lane) = make_float2(c3[0],c3[1]);
      }
    }
    if(warp<10){
      if(warp>=8) mb_wait(mbase+8*MB_W, 0);
      asm volatile("bar.sync 12, 320;" ::: "memory");
      float a=0;
      #pragma unroll
      for(int i=0;i<8;i++) a += part[i*32+lane];
      a = rbf(a);
      const float u = __shfl_down_sync(0xffffffffu, a, 16);
      const float guv = rbf(rbf(__fdividef(a, 1.0f+__expf(-a))) * u);
      const uint32_t* wd = (const uint32_t*)(sm + OFF_WD) + tid;
      float a0=0,a1=0;
      #pragma unroll
      for(int i=0;i<16;i++){
        const float gq = __shfl_sync(0xffffffffu, guv, i);
        const uint32_t w0 = wd[i*320];
        a0 = fmaf(gq, bflo(w0), a0); a1 = fmaf(gq, bfhi(w0), a1);
      }
      stg_rlx2(g_yp + (size_t)b*D_ + 2*tid, make_uint2(~__float_as_uint(a0), ~__float_as_uint(a1)));
    }
    if(b<40){
      float* part2 = (float*)(sm + OFF_RED);
      if(tid<NFF*4){
        const float* p = g_yp + (size_t)(tid>>2)*D_ + b*16 + (tid&3)*4;
        __nanosleep(YD);
        uint4 a = ldg_rlx(p); int it=0;
        while((a.x==0u||a.y==0u||a.z==0u||a.w==0u) && ++it<SPIN_MAX){ __nanosleep(64); a = ldg_rlx(p); }
        float f0=__uint_as_float(~a.x), f1=__uint_as_float(~a.y), f2=__uint_as_float(~a.z), f3=__uint_as_float(~a.w);
        #pragma unroll
        for(int o2=4;o2<32;o2<<=1){
          f0 += __shfl_xor_sync(0xffffffffu,f0,o2); f1 += __shfl_xor_sync(0xffffffffu,f1,o2);
          f2 += __shfl_xor_sync(0xffffffffu,f2,o2); f3 += __shfl_xor_sync(0xffffffffu,f3,o2);
        }
        if(lane<4) *(float4*)(part2 + warp*16 + lane*4) = make_float4(f0,f1,f2,f3);
        asm volatile("bar.sync 13, 384;" ::: "memory");
      }
      if(tid<16){
        float a2=0;
        #pragma unroll
        for(int i=0;i<NFF/8;i++) a2 += part2[i*16+tid];
        float rsel = rbf(__fdividef(1.0f, 1.0f+__expf(-wrr)));
        float y = rbf(rbf(a2)*rsel);
        float xv = __bfloat162float(((const bf16*)(sm+OFF_XSEL))[b*16+tid]);
        float hv = __bfloat162float(((const bf16*)(sm+OFF_XSEL))[D_+tid]);
        out[(size_t)widx*D_ + b*16 + tid] = __float2bfloat16_rn(hv + rbf(xv + y));
      }
    }
  }
  }
done:
  if(lane==0) asm volatile("cp.async.bulk.wait_group.read 0;" ::: "memory");
}

typedef CUresult (*EncodeTiledFn)(CUtensorMap*, CUtensorMapDataType, cuuint32_t, void*, const cuuint64_t*, const cuuint64_t*, const cuuint32_t*, const cuuint32_t*,
                                  CUtensorMapInterleave, CUtensorMapSwizzle, CUtensorMapL2promotion, CUtensorMapFloatOOBfill);
extern "C" void kernel_launch(void* const* d_in, const int* in_sizes, int n_in, void* d_out, int out_size) {
  void* fn = nullptr; cudaDriverEntryPointQueryResult qr;
  cudaGetDriverEntryPoint("cuTensorMapEncodeTiled", &fn, cudaEnableDefault, &qr);
  CUtensorMap tg, tu, tk, tv, tx;
  {
    void* kvp = nullptr; cudaGetSymbolAddress(&kvp, g_kvx);
    cuuint64_t gd3[2] = {2048, (cuuint64_t)CH*NCTA}; cuuint64_t gs3[1] = {4096}; cuuint32_t bx3[2] = {8, 128}; cuuint32_t es3[2] = {1, 1};
    ((EncodeTiledFn)fn)(&tx, CU_TENSOR_MAP_DATA_TYPE_BFLOAT16, 2, kvp, gd3, gs3, bx3, es3, CU_TENSOR_MAP_INTERLEAVE_NONE, CU_TENSOR_MAP_SWIZZLE_NONE, CU_TENSOR_MAP_L2_PROMOTION_NONE, CU_TENSOR_MAP_FLOAT_OOB_FILL_NONE);
  }
  {
    cuuint64_t gd2[2] = {(cuuint64_t)D_, (cuuint64_t)S_}; cuuint64_t gs2[1] = {(cuuint64_t)D_*2}; cuuint32_t bk[2] = {128, 19}, bv[2] = {128, 16}; cuuint32_t es2[2] = {1, 1};
    ((EncodeTiledFn)fn)(&tk, CU_TENSOR_MAP_DATA_TYPE_BFLOAT16, 2, d_in[1], gd2, gs2, bk, es2, CU_TENSOR_MAP_INTERLEAVE_NONE, CU_TENSOR_MAP_SWIZZLE_NONE, CU_TENSOR_MAP_L2_PROMOTION_NONE, CU_TENSOR_MAP_FLOAT_OOB_FILL_NONE);
    ((EncodeTiledFn)fn)(&tv, CU_TENSOR_MAP_DATA_TYPE_BFLOAT16, 2, d_in[2], gd2, gs2, bv, es2, CU_TENSOR_MAP_INTERLEAVE_NONE, CU_TENSOR_MAP_SWIZZLE_NONE, CU_TENSOR_MAP_L2_PROMOTION_NONE, CU_TENSOR_MAP_FLOAT_OOB_FILL_NONE);
  }
  cuuint64_t gd[2] = {(cuuint64_t)F_, (cuuint64_t)D_}; cuuint64_t gs[1] = {(cuuint64_t)F_*2}; cuuint32_t bx[2] = {16, 128}; cuuint32_t es[2] = {1, 1};
  ((EncodeTiledFn)fn)(&tg, CU_TENSOR_MAP_DATA_TYPE_BFLOAT16, 2, d_in[8], gd, gs, bx, es, CU_TENSOR_MAP_INTERLEAVE_NONE, CU_TENSOR_MAP_SWIZZLE_NONE, CU_TENSOR_MAP_L2_PROMOTION_NONE, CU_TENSOR_MAP_FLOAT_OOB_FILL_NONE);
  ((EncodeTiledFn)fn)(&tu, CU_TENSOR_MAP_DATA_TYPE_BFLOAT16, 2, d_in[9], gd, gs, bx, es, CU_TENSOR_MAP_INTERLEAVE_NONE, CU_TENSOR_MAP_SWIZZLE_NONE, CU_TENSOR_MAP_L2_PROMOTION_NONE, CU_TENSOR_MAP_FLOAT_OOB_FILL_NONE);
  cudaFuncSetAttribute(fused_kernel, cudaFuncAttributeMaxDynamicSharedMemorySize, SMEM_BYTES);
  fused_kernel<<<NCTA, NT, SMEM_BYTES>>>((const bf16*)d_in[0], tk, tv, (const bf16*)d_in[3],
      (const bf16*)d_in[4], (const bf16*)d_in[5], (const bf16*)d_in[7], tx, tg, tu, (const bf16*)d_in[8], (const bf16*)d_in[9], (const bf16*)d_in[10], (bf16*)d_out);
}
```
